```python
import torch

def _softmax(x, axis=-1):
    return torch.softmax(x, dim=axis)
def _gelu(x):
    return torch.nn.functional.gelu(x, approximate="tanh")
def _silu(x):
    return torch.nn.functional.silu(x)
def _sigmoid(x):
    return torch.sigmoid(x)
def _layernorm(x, axis=-1, eps=1e-5):
    m = x.mean(dim=axis, keepdim=True)
    v = x.var(dim=axis, keepdim=True, unbiased=False)
    return (x - m) / torch.sqrt(v + eps)
def _scatter_add(tgt, idx, src, axis=0):
    return tgt.clone().index_add_(axis, idx, src)
def _segment_sum(src, seg, n):
    out = torch.zeros((n,) + src.shape[1:], dtype=src.dtype)
    return out.index_add_(0, seg, src)
def _pad(x, pw):
    flat = tuple(v for pair in reversed(pw) for v in pair)
    return torch.nn.functional.pad(x, flat)

kernel_name = 'parallel_sum__grouped_kv_mqa__geglu_ffn__prompt'

def setup_inputs():

    _w = (lambda a: (lambda t: t.to(torch.bfloat16) if t.is_floating_point() else t)(torch.as_tensor(a)))
    def _A_setup():
        B, S, D, H = 1, 2048, 640, 32
        Dh = D // H
        return {
            "x": _w((lambda *s: torch.randn(*s, dtype=torch.bfloat16) * 0.05)(B, S, D)),
            "wq": _w((lambda *s: torch.randn(*s, dtype=torch.bfloat16) * 0.2)(D, H * Dh)),
            "wk": _w((lambda *s: torch.randn(*s, dtype=torch.bfloat16) * 0.2)(D, Dh)),
            "wv": _w((lambda *s: torch.randn(*s, dtype=torch.bfloat16) * 0.1)(D, Dh)),
            "wo": _w((lambda *s: torch.randn(*s, dtype=torch.bfloat16) * 0.1)(H * Dh, D)),
        }
    _A_in = _A_setup()

    def _B_setup():
        B, S, D, F = 1, 2048, 640, 1536
        return {
            "x": _w((lambda *s: torch.randn(*s, dtype=torch.bfloat16) * 0.05)(B, S, D)),
            "w_gate": _w((lambda *s: torch.randn(*s, dtype=torch.bfloat16) * 0.1)(D, F)),
            "w_up": _w((lambda *s: torch.randn(*s, dtype=torch.bfloat16) * 0.1)(D, F)),
            "w_down": _w((lambda *s: torch.randn(*s, dtype=torch.bfloat16) * 0.1)(F, D)),
        }
    _B_in = _B_setup()

    return {
        "A_x": _A_in["x"],
        "A_wq": _A_in["wq"],
        "A_wk": _A_in["wk"],
        "A_wv": _A_in["wv"],
        "A_wo": _A_in["wo"],
        "B_x": _B_in["x"],
        "B_w_gate": _B_in["w_gate"],
        "B_w_up": _B_in["w_up"],
        "B_w_down": _B_in["w_down"],
    }

def reference(A_x, A_wq, A_wk, A_wv, A_wo, B_x, B_w_gate, B_w_up, B_w_down):
    def _A_ref(x, wq, wk, wv, wo):
        B, S, D = x.shape
        H = 32
        Dh = D // H
        q = (lambda x, *d: x.permute(*d))((x @ wq).reshape(B, S, H, Dh), 0, 2, 1, 3)
        k = x @ wk
        v = x @ wv
        scores = torch.einsum("bhqd,bkd->bhqk", q, k) * (Dh ** -0.5)
        p = _softmax(scores, axis=-1)
        o = torch.einsum("bhqk,bkd->bhqd", p, v)
        return (lambda x, *d: x.permute(*d))(o, 0, 2, 1, 3).reshape(B, S, H * Dh) @ wo

    def _B_ref(x, w_gate, w_up, w_down):
        return (_gelu(x @ w_gate) * (x @ w_up)) @ w_down

    x = A_x
    xn = _layernorm(x, axis=-1)
    return x + _A_ref(xn, A_wq, A_wk, A_wv, A_wo) + _B_ref(xn, B_w_gate, B_w_up, B_w_down)
```

```cpp
#pragma nv_diag_suppress 177
#include <cuda_runtime.h>
#include <cuda_bf16.h>
#include <cuda_fp16.h>
#include <cuda.h>
#include <stdint.h>

#define ATT_NM 4
#define ATT_PMASK ((0xFF << ATT_NM) & 0xFF)
namespace {
constexpr int S_LEN = 2048, DM = 640, NH = 32, DH = 20, FF = 1536;
typedef __nv_bfloat16 bf16;

__device__ __align__(1024) bf16 g_xn[S_LEN * DM];
__device__ __align__(1024) bf16 g_q[S_LEN * DM];
__device__ __align__(1024) uint8_t g_kimg[S_LEN * 48];
__device__ __align__(1024) uint8_t g_vimg[S_LEN * 48];
__device__ __align__(1024) bf16 g_wpk[DM * 128];
__device__ __align__(1024) bf16 g_oh[S_LEN * (DM + FF)];

__device__ __forceinline__ uint32_t smem_u32(const void* p) { return (uint32_t)__cvta_generic_to_shared(p); }
__device__ __forceinline__ void mbar_init(uint32_t b, int c) { asm volatile("mbarrier.init.shared::cta.b64 [%0], %1;" ::"r"(b), "r"(c) : "memory"); }
__device__ __forceinline__ void mbar_expect(uint32_t b, uint32_t bytes) { asm volatile("mbarrier.arrive.expect_tx.shared::cta.b64 _, [%0], %1;" ::"r"(b), "r"(bytes) : "memory"); }
__device__ __forceinline__ void mbar_arrive(uint32_t b) { asm volatile("mbarrier.arrive.shared::cta.b64 _, [%0];" ::"r"(b) : "memory"); }
__device__ __forceinline__ void mbar_arrive_cluster(uint32_t b, uint32_t cta) {
  asm volatile("{\n.reg .b32 ra;\nmapa.shared::cluster.u32 ra, %0, %1;\nmbarrier.arrive.release.cluster.shared::cluster.b64 _, [ra];\n}" ::"r"(b), "r"(cta) : "memory");
}
__device__ __forceinline__ void mbar_arrive_remote(uint32_t b, uint32_t cta) {
  asm volatile("{\n.reg .b32 ra;\nmapa.shared::cluster.u32 ra, %0, %1;\nmbarrier.arrive.shared::cluster.b64 _, [ra];\n}" ::"r"(b), "r"(cta) : "memory");
}
__device__ __forceinline__ bool mbar_test(uint32_t b, uint32_t ph) {
  uint32_t r;
  asm volatile("{\n.reg .pred p;\nmbarrier.test_wait.parity.shared::cta.b64 p, [%1], %2;\nselp.u32 %0, 1, 0, p;\n}" : "=r"(r) : "r"(b), "r"(ph) : "memory");
  return r;
}
__device__ __forceinline__ void mbar_wait(uint32_t b, uint32_t ph) {
  asm volatile("{\n.reg .pred p;\n.reg .u32 n;\nmbarrier.try_wait.parity.shared::cta.b64 p, [%0], %1;\n@p bra WD;\nmov.u32 n, 0;\nWL:\nmbarrier.try_wait.parity.shared::cta.b64 p, [%0], %1;\n@p bra WD;\nadd.u32 n, n, 1;\nsetp.lt.u32 p, n, 8000000;\n@p bra WL;\ntrap;\nWD:\n}" ::"r"(b), "r"(ph) : "memory");
}
__device__ __forceinline__ void mbar_wait_cluster(uint32_t b, uint32_t ph) {
  asm volatile("{\n.reg .pred p;\n.reg .u32 n;\nmbarrier.try_wait.parity.acquire.cluster.shared::cta.b64 p, [%0], %1;\n@p bra WD;\nmov.u32 n, 0;\nWL:\nmbarrier.try_wait.parity.acquire.cluster.shared::cta.b64 p, [%0], %1;\n@p bra WD;\nadd.u32 n, n, 1;\nsetp.lt.u32 p, n, 8000000;\n@p bra WL;\ntrap;\nWD:\n}" ::"r"(b), "r"(ph) : "memory");
}
__device__ __forceinline__ void fence_mbar_init() { asm volatile("fence.mbarrier_init.release.cluster;" ::: "memory"); }
__device__ __forceinline__ void fence_async_smem() { asm volatile("fence.proxy.async.shared::cta;" ::: "memory"); }
__device__ __forceinline__ void bulk_g2s(uint32_t dst, const void* src, uint32_t bytes, uint32_t bar) {
  asm volatile("cp.async.bulk.shared::cluster.global.mbarrier::complete_tx::bytes [%0], [%1], %2, [%3];" ::"r"(dst), "l"(src), "r"(bytes), "r"(bar) : "memory");
}
__device__ __forceinline__ void tma_2d(uint32_t dst, const CUtensorMap* tm, int c0, int c1, uint32_t bar) {
  asm volatile("cp.async.bulk.tensor.2d.shared::cluster.global.mbarrier::complete_tx::bytes [%0], [%1, {%3,%4}], [%2];" ::"r"(dst), "l"(tm), "r"(bar), "r"(c0), "r"(c1) : "memory");
}
__device__ __forceinline__ void tma_2d_mc(uint32_t dst, const CUtensorMap* tm, int c0, int c1, uint32_t bar, uint16_t mask) {
  asm volatile("cp.async.bulk.tensor.2d.shared::cluster.global.mbarrier::complete_tx::bytes.multicast::cluster [%0], [%1, {%3,%4}], [%2], %5;" ::"r"(dst), "l"(tm), "r"(bar), "r"(c0), "r"(c1), "h"(mask) : "memory");
}
__device__ __forceinline__ void tma_3d(uint32_t dst, const CUtensorMap* tm, int c0, int c1, int c2, uint32_t bar) {
  asm volatile("cp.async.bulk.tensor.3d.shared::cluster.global.mbarrier::complete_tx::bytes [%0], [%1, {%3,%4,%5}], [%2];" ::"r"(dst), "l"(tm), "r"(bar), "r"(c0), "r"(c1), "r"(c2) : "memory");
}
__device__ __forceinline__ void l2_prefetch(const void* p, uint32_t bytes) { asm volatile("cp.async.bulk.prefetch.L2.global [%0], %1;" ::"l"(p), "r"(bytes) : "memory"); }
__device__ __forceinline__ uint32_t cta_rank() { uint32_t r; asm("mov.u32 %0, %%cluster_ctarank;" : "=r"(r)); return r; }
__device__ __forceinline__ uint32_t mapa(uint32_t a, uint32_t cta) { uint32_t r; asm("mapa.shared::cluster.u32 %0, %1, %2;" : "=r"(r) : "r"(a), "r"(cta)); return r; }
__device__ __forceinline__ void prefetch_tm(const CUtensorMap* tm) { asm volatile("prefetch.tensormap [%0];" ::"l"(tm) : "memory"); }
__device__ __forceinline__ void pdl_wait() { asm volatile("griddepcontrol.wait;" ::: "memory"); }
__device__ __forceinline__ void pdl_trigger() { asm volatile("griddepcontrol.launch_dependents;" ::: "memory"); }
__device__ __forceinline__ void cluster_sync_all() { asm volatile("barrier.cluster.arrive.release.aligned;\nbarrier.cluster.wait.acquire.aligned;" ::: "memory"); }
__device__ __forceinline__ void wg_fence() { asm volatile("wgmma.fence.sync.aligned;" ::: "memory"); }
__device__ __forceinline__ void wg_commit() { asm volatile("wgmma.commit_group.sync.aligned;" ::: "memory"); }
template <int N> __device__ __forceinline__ void wg_wait() { asm volatile("wgmma.wait_group.sync.aligned %0;" ::"n"(N) : "memory"); }
template <int N> __device__ __forceinline__ void reg_fence(float (&d)[N]) {
#pragma unroll
  for (int i = 0; i < N; i++) asm volatile("" : "+f"(d[i])::"memory");
}
template <int N> __device__ __forceinline__ void ureg_fence(uint32_t (&d)[N]) {
#pragma unroll
  for (int i = 0; i < N; i++) asm volatile("" : "+r"(d[i])::"memory");
}
__device__ __forceinline__ uint32_t packh(float lo, float hi) { uint32_t r; asm("cvt.rn.f16x2.f32 %0, %1, %2;" : "=r"(r) : "f"(hi), "f"(lo)); return r; }
__device__ __forceinline__ uint64_t mkdesc(uint32_t addr, uint32_t lbo, uint32_t sbo, int swz) {
  return (uint64_t)((addr & 0x3FFFF) >> 4) | ((uint64_t)(lbo >> 4) << 16) | ((uint64_t)(sbo >> 4) << 32) | ((uint64_t)swz << 62);
}
__device__ __forceinline__ float ex2(float x) { float y; asm("ex2.approx.ftz.f32 %0, %1;" : "=f"(y) : "f"(x)); return y; }
__device__ __forceinline__ uint32_t packbf(float lo, float hi) { uint32_t r; asm("cvt.rn.bf16x2.f32 %0, %1, %2;" : "=r"(r) : "f"(hi), "f"(lo)); return r; }
__device__ __forceinline__ float bflo(uint32_t v) { return __uint_as_float(v << 16); }
__device__ __forceinline__ float bfhi(uint32_t v) { return __uint_as_float(v & 0xFFFF0000u); }
__device__ __forceinline__ void wgmma_h_m64n64k16_rs(uint32_t (&d)[16], uint32_t a0, uint32_t a1, uint32_t a2, uint32_t a3, uint64_t db, int sd) {
  asm volatile("{\n.reg .pred p;\nsetp.ne.b32 p, %21, 0;\n"
    "wgmma.mma_async.sync.aligned.m64n64k16.f16.f16.f16 {%0, %1, %2, %3, %4, %5, %6, %7, %8, %9, %10, %11, %12, %13, %14, %15}, {%16,%17,%18,%19}, %20, p, 1, 1, 0;\n}\n"
    : "+r"(d[0]), "+r"(d[1]), "+r"(d[2]), "+r"(d[3]), "+r"(d[4]), "+r"(d[5]), "+r"(d[6]), "+r"(d[7]), "+r"(d[8]), "+r"(d[9]), "+r"(d[10]), "+r"(d[11]), "+r"(d[12]), "+r"(d[13]), "+r"(d[14]), "+r"(d[15]) : "r"(a0), "r"(a1), "r"(a2), "r"(a3), "l"(db), "r"(sd));
}
__device__ __forceinline__ void wgmma_hh_rs(uint32_t (&d)[6], uint32_t a0, uint32_t a1, uint32_t a2, uint32_t a3, uint64_t db, int sd) {
  asm volatile("{\n.reg .pred p;\nsetp.ne.b32 p, %11, 0;\n"
    "wgmma.mma_async.sync.aligned.m64n24k16.f16.f16.f16 {%0, %1, %2, %3, %4, %5}, {%6,%7,%8,%9}, %10, p, 1, 1, 0;\n}\n"
    : "+r"(d[0]), "+r"(d[1]), "+r"(d[2]), "+r"(d[3]), "+r"(d[4]), "+r"(d[5]) : "r"(a0), "r"(a1), "r"(a2), "r"(a3), "l"(db), "r"(sd));
}
__device__ __forceinline__ void wgmma_hf_rs(float (&d)[12], uint32_t a0, uint32_t a1, uint32_t a2, uint32_t a3, uint64_t db, int sd) {
  asm volatile("{\n.reg .pred p;\nsetp.ne.b32 p, %17, 0;\n"
    "wgmma.mma_async.sync.aligned.m64n24k16.f32.f16.f16 {%0, %1, %2, %3, %4, %5, %6, %7, %8, %9, %10, %11}, {%12,%13,%14,%15}, %16, p, 1, 1, 0;\n}\n"
    : "+f"(d[0]), "+f"(d[1]), "+f"(d[2]), "+f"(d[3]), "+f"(d[4]), "+f"(d[5]), "+f"(d[6]), "+f"(d[7]), "+f"(d[8]), "+f"(d[9]), "+f"(d[10]), "+f"(d[11]) : "r"(a0), "r"(a1), "r"(a2), "r"(a3), "l"(db), "r"(sd));
}
__device__ __forceinline__ void wgmma_hh_rs(uint32_t (&d)[8], uint32_t a0, uint32_t a1, uint32_t a2, uint32_t a3, uint64_t db, int sd) {
  asm volatile("{\n.reg .pred p;\nsetp.ne.b32 p, %13, 0;\n"
    "wgmma.mma_async.sync.aligned.m64n32k16.f16.f16.f16 {%0, %1, %2, %3, %4, %5, %6, %7}, {%8,%9,%10,%11}, %12, p, 1, 1, 0;\n}\n"
    : "+r"(d[0]), "+r"(d[1]), "+r"(d[2]), "+r"(d[3]), "+r"(d[4]), "+r"(d[5]), "+r"(d[6]), "+r"(d[7]) : "r"(a0), "r"(a1), "r"(a2), "r"(a3), "l"(db), "r"(sd));
}
__device__ __forceinline__ void wgmma_hf_rs(float (&d)[16], uint32_t a0, uint32_t a1, uint32_t a2, uint32_t a3, uint64_t db, int sd) {
  asm volatile("{\n.reg .pred p;\nsetp.ne.b32 p, %21, 0;\n"
    "wgmma.mma_async.sync.aligned.m64n32k16.f32.f16.f16 {%0, %1, %2, %3, %4, %5, %6, %7, %8, %9, %10, %11, %12, %13, %14, %15}, {%16,%17,%18,%19}, %20, p, 1, 1, 0;\n}\n"
    : "+f"(d[0]), "+f"(d[1]), "+f"(d[2]), "+f"(d[3]), "+f"(d[4]), "+f"(d[5]), "+f"(d[6]), "+f"(d[7]), "+f"(d[8]), "+f"(d[9]), "+f"(d[10]), "+f"(d[11]), "+f"(d[12]), "+f"(d[13]), "+f"(d[14]), "+f"(d[15]) : "r"(a0), "r"(a1), "r"(a2), "r"(a3), "l"(db), "r"(sd));
}
__device__ __forceinline__ void wgmma_hh_rs(uint32_t (&d)[10], uint32_t a0, uint32_t a1, uint32_t a2, uint32_t a3, uint64_t db, int sd) {
  asm volatile("{\n.reg .pred p;\nsetp.ne.b32 p, %15, 0;\n"
    "wgmma.mma_async.sync.aligned.m64n40k16.f16.f16.f16 {%0, %1, %2, %3, %4, %5, %6, %7, %8, %9}, {%10,%11,%12,%13}, %14, p, 1, 1, 0;\n}\n"
    : "+r"(d[0]), "+r"(d[1]), "+r"(d[2]), "+r"(d[3]), "+r"(d[4]), "+r"(d[5]), "+r"(d[6]), "+r"(d[7]), "+r"(d[8]), "+r"(d[9]) : "r"(a0), "r"(a1), "r"(a2), "r"(a3), "l"(db), "r"(sd));
}
__device__ __forceinline__ void wgmma_hf_rs(float (&d)[20], uint32_t a0, uint32_t a1, uint32_t a2, uint32_t a3, uint64_t db, int sd) {
  asm volatile("{\n.reg .pred p;\nsetp.ne.b32 p, %25, 0;\n"
    "wgmma.mma_async.sync.aligned.m64n40k16.f32.f16.f16 {%0, %1, %2, %3, %4, %5, %6, %7, %8, %9, %10, %11, %12, %13, %14, %15, %16, %17, %18, %19}, {%20,%21,%22,%23}, %24, p, 1, 1, 0;\n}\n"
    : "+f"(d[0]), "+f"(d[1]), "+f"(d[2]), "+f"(d[3]), "+f"(d[4]), "+f"(d[5]), "+f"(d[6]), "+f"(d[7]), "+f"(d[8]), "+f"(d[9]), "+f"(d[10]), "+f"(d[11]), "+f"(d[12]), "+f"(d[13]), "+f"(d[14]), "+f"(d[15]), "+f"(d[16]), "+f"(d[17]), "+f"(d[18]), "+f"(d[19]) : "r"(a0), "r"(a1), "r"(a2), "r"(a3), "l"(db), "r"(sd));
}
__device__ __forceinline__ void wgmma_m64n64k16_rs_tb0(float (&d)[32], uint32_t a0, uint32_t a1, uint32_t a2, uint32_t a3, uint64_t db, int sd) {
  asm volatile("{\n.reg .pred p;\nsetp.ne.b32 p, %37, 0;\n"
    "wgmma.mma_async.sync.aligned.m64n64k16.f32.bf16.bf16 {%0, %1, %2, %3, %4, %5, %6, %7, %8, %9, %10, %11, %12, %13, %14, %15, %16, %17, %18, %19, %20, %21, %22, %23, %24, %25, %26, %27, %28, %29, %30, %31}, {%32,%33,%34,%35}, %36, p, 1, 1, 0;\n}\n"
    : "+f"(d[0]), "+f"(d[1]), "+f"(d[2]), "+f"(d[3]), "+f"(d[4]), "+f"(d[5]), "+f"(d[6]), "+f"(d[7]), "+f"(d[8]), "+f"(d[9]), "+f"(d[10]), "+f"(d[11]), "+f"(d[12]), "+f"(d[13]), "+f"(d[14]), "+f"(d[15]), "+f"(d[16]), "+f"(d[17]), "+f"(d[18]), "+f"(d[19]), "+f"(d[20]), "+f"(d[21]), "+f"(d[22]), "+f"(d[23]), "+f"(d[24]), "+f"(d[25]), "+f"(d[26]), "+f"(d[27]), "+f"(d[28]), "+f"(d[29]), "+f"(d[30]), "+f"(d[31]) : "r"(a0), "r"(a1), "r"(a2), "r"(a3), "l"(db), "r"(sd));
}
__device__ __forceinline__ void wgmma_m64n24k16_rs_tb1(float (&d)[12], uint32_t a0, uint32_t a1, uint32_t a2, uint32_t a3, uint64_t db, int sd) {
  asm volatile("{\n.reg .pred p;\nsetp.ne.b32 p, %17, 0;\n"
    "wgmma.mma_async.sync.aligned.m64n24k16.f32.bf16.bf16 {%0, %1, %2, %3, %4, %5, %6, %7, %8, %9, %10, %11}, {%12,%13,%14,%15}, %16, p, 1, 1, 1;\n}\n"
    : "+f"(d[0]), "+f"(d[1]), "+f"(d[2]), "+f"(d[3]), "+f"(d[4]), "+f"(d[5]), "+f"(d[6]), "+f"(d[7]), "+f"(d[8]), "+f"(d[9]), "+f"(d[10]), "+f"(d[11]) : "r"(a0), "r"(a1), "r"(a2), "r"(a3), "l"(db), "r"(sd));
}
__device__ __forceinline__ void wgmma_m64n160k16_ss_tb1(float (&d)[80], uint64_t da, uint64_t db, int sd) {
  asm volatile("{\n.reg .pred p;\nsetp.ne.b32 p, %82, 0;\n"
    "wgmma.mma_async.sync.aligned.m64n160k16.f32.bf16.bf16 {%0, %1, %2, %3, %4, %5, %6, %7, %8, %9, %10, %11, %12, %13, %14, %15, %16, %17, %18, %19, %20, %21, %22, %23, %24, %25, %26, %27, %28, %29, %30, %31, %32, %33, %34, %35, %36, %37, %38, %39, %40, %41, %42, %43, %44, %45, %46, %47, %48, %49, %50, %51, %52, %53, %54, %55, %56, %57, %58, %59, %60, %61, %62, %63, %64, %65, %66, %67, %68, %69, %70, %71, %72, %73, %74, %75, %76, %77, %78, %79}, %80, %81, p, 1, 1, 0, 1;\n}\n"
    : "+f"(d[0]), "+f"(d[1]), "+f"(d[2]), "+f"(d[3]), "+f"(d[4]), "+f"(d[5]), "+f"(d[6]), "+f"(d[7]), "+f"(d[8]), "+f"(d[9]), "+f"(d[10]), "+f"(d[11]), "+f"(d[12]), "+f"(d[13]), "+f"(d[14]), "+f"(d[15]), "+f"(d[16]), "+f"(d[17]), "+f"(d[18]), "+f"(d[19]), "+f"(d[20]), "+f"(d[21]), "+f"(d[22]), "+f"(d[23]), "+f"(d[24]), "+f"(d[25]), "+f"(d[26]), "+f"(d[27]), "+f"(d[28]), "+f"(d[29]), "+f"(d[30]), "+f"(d[31]), "+f"(d[32]), "+f"(d[33]), "+f"(d[34]), "+f"(d[35]), "+f"(d[36]), "+f"(d[37]), "+f"(d[38]), "+f"(d[39]), "+f"(d[40]), "+f"(d[41]), "+f"(d[42]), "+f"(d[43]), "+f"(d[44]), "+f"(d[45]), "+f"(d[46]), "+f"(d[47]), "+f"(d[48]), "+f"(d[49]), "+f"(d[50]), "+f"(d[51]), "+f"(d[52]), "+f"(d[53]), "+f"(d[54]), "+f"(d[55]), "+f"(d[56]), "+f"(d[57]), "+f"(d[58]), "+f"(d[59]), "+f"(d[60]), "+f"(d[61]), "+f"(d[62]), "+f"(d[63]), "+f"(d[64]), "+f"(d[65]), "+f"(d[66]), "+f"(d[67]), "+f"(d[68]), "+f"(d[69]), "+f"(d[70]), "+f"(d[71]), "+f"(d[72]), "+f"(d[73]), "+f"(d[74]), "+f"(d[75]), "+f"(d[76]), "+f"(d[77]), "+f"(d[78]), "+f"(d[79]) : "l"(da), "l"(db), "r"(sd));
}
__device__ __forceinline__ void wgmma_m64n128k16_ss_tb1(float (&d)[64], uint64_t da, uint64_t db, int sd) {
  asm volatile("{\n.reg .pred p;\nsetp.ne.b32 p, %66, 0;\n"
    "wgmma.mma_async.sync.aligned.m64n128k16.f32.bf16.bf16 {%0, %1, %2, %3, %4, %5, %6, %7, %8, %9, %10, %11, %12, %13, %14, %15, %16, %17, %18, %19, %20, %21, %22, %23, %24, %25, %26, %27, %28, %29, %30, %31, %32, %33, %34, %35, %36, %37, %38, %39, %40, %41, %42, %43, %44, %45, %46, %47, %48, %49, %50, %51, %52, %53, %54, %55, %56, %57, %58, %59, %60, %61, %62, %63}, %64, %65, p, 1, 1, 0, 1;\n}\n"
    : "+f"(d[0]), "+f"(d[1]), "+f"(d[2]), "+f"(d[3]), "+f"(d[4]), "+f"(d[5]), "+f"(d[6]), "+f"(d[7]), "+f"(d[8]), "+f"(d[9]), "+f"(d[10]), "+f"(d[11]), "+f"(d[12]), "+f"(d[13]), "+f"(d[14]), "+f"(d[15]), "+f"(d[16]), "+f"(d[17]), "+f"(d[18]), "+f"(d[19]), "+f"(d[20]), "+f"(d[21]), "+f"(d[22]), "+f"(d[23]), "+f"(d[24]), "+f"(d[25]), "+f"(d[26]), "+f"(d[27]), "+f"(d[28]), "+f"(d[29]), "+f"(d[30]), "+f"(d[31]), "+f"(d[32]), "+f"(d[33]), "+f"(d[34]), "+f"(d[35]), "+f"(d[36]), "+f"(d[37]), "+f"(d[38]), "+f"(d[39]), "+f"(d[40]), "+f"(d[41]), "+f"(d[42]), "+f"(d[43]), "+f"(d[44]), "+f"(d[45]), "+f"(d[46]), "+f"(d[47]), "+f"(d[48]), "+f"(d[49]), "+f"(d[50]), "+f"(d[51]), "+f"(d[52]), "+f"(d[53]), "+f"(d[54]), "+f"(d[55]), "+f"(d[56]), "+f"(d[57]), "+f"(d[58]), "+f"(d[59]), "+f"(d[60]), "+f"(d[61]), "+f"(d[62]), "+f"(d[63]) : "l"(da), "l"(db), "r"(sd));
}
__device__ __forceinline__ void wgmma_m64n88k16_ss_tb1(float (&d)[44], uint64_t da, uint64_t db, int sd) {
  asm volatile("{\n.reg .pred p;\nsetp.ne.b32 p, %46, 0;\n"
    "wgmma.mma_async.sync.aligned.m64n88k16.f32.bf16.bf16 {%0, %1, %2, %3, %4, %5, %6, %7, %8, %9, %10, %11, %12, %13, %14, %15, %16, %17, %18, %19, %20, %21, %22, %23, %24, %25, %26, %27, %28, %29, %30, %31, %32, %33, %34, %35, %36, %37, %38, %39, %40, %41, %42, %43}, %44, %45, p, 1, 1, 0, 1;\n}\n"
    : "+f"(d[0]), "+f"(d[1]), "+f"(d[2]), "+f"(d[3]), "+f"(d[4]), "+f"(d[5]), "+f"(d[6]), "+f"(d[7]), "+f"(d[8]), "+f"(d[9]), "+f"(d[10]), "+f"(d[11]), "+f"(d[12]), "+f"(d[13]), "+f"(d[14]), "+f"(d[15]), "+f"(d[16]), "+f"(d[17]), "+f"(d[18]), "+f"(d[19]), "+f"(d[20]), "+f"(d[21]), "+f"(d[22]), "+f"(d[23]), "+f"(d[24]), "+f"(d[25]), "+f"(d[26]), "+f"(d[27]), "+f"(d[28]), "+f"(d[29]), "+f"(d[30]), "+f"(d[31]), "+f"(d[32]), "+f"(d[33]), "+f"(d[34]), "+f"(d[35]), "+f"(d[36]), "+f"(d[37]), "+f"(d[38]), "+f"(d[39]), "+f"(d[40]), "+f"(d[41]), "+f"(d[42]), "+f"(d[43]) : "l"(da), "l"(db), "r"(sd));
}

}

namespace {
__device__ __forceinline__ uint32_t exp2_pair_h(uint32_t x) {
  uint32_t t, r, f, g;
  asm("max.f16x2 %0, %1, %2;" : "=r"(x) : "r"(x), "r"(0xD7F0D7F0u));
  asm("min.f16x2 %0, %1, %2;" : "=r"(x) : "r"(x), "r"(0x58005800u));
  asm("add.rn.f16x2 %0, %1, %2;" : "=r"(t) : "r"(x), "r"(0x65B665B7u));
  asm("sub.rn.f16x2 %0, %1, %2;" : "=r"(r) : "r"(t), "r"(0x65B665B7u));
  asm("sub.rn.f16x2 %0, %1, %2;" : "=r"(f) : "r"(x), "r"(r));
  asm("fma.rn.f16x2 %0, %1, %2, %3;" : "=r"(g) : "r"(0x491F491Fu), "r"(f), "r"(0x517E517Eu));
  asm("fma.rn.f16x2 %0, %1, %2, %3;" : "=r"(g) : "r"(g), "r"(f), "r"(0x57D757D7u));
  asm("fma.rn.f16x2 %0, %1, %2, %3;" : "=r"(g) : "r"(g), "r"(f), "r"(0x64826435u));
  return t * 128u + g;
}
__device__ __forceinline__ float hlo(uint32_t v) { return __half2float(__ushort_as_half((unsigned short)(v & 0xFFFF))); }
__device__ __forceinline__ float hhi(uint32_t v) { return __half2float(__ushort_as_half((unsigned short)(v >> 16))); }
__device__ __forceinline__ uint32_t hmax2(uint32_t a, uint32_t b) { uint32_t r; asm("max.f16x2 %0, %1, %2;" : "=r"(r) : "r"(a), "r"(b)); return r; }
__device__ __forceinline__ uint32_t hmin2(uint32_t a, uint32_t b) { uint32_t r; asm("min.f16x2 %0, %1, %2;" : "=r"(r) : "r"(a), "r"(b)); return r; }
__device__ __noinline__ void attn_row_exact(const uint8_t* smem, int R) {
  const int lane = threadIdx.x & 31;
  float q[DH];
#pragma unroll
  for (int d = 0; d < DH; d++) q[d] = __half2float(((const __half*)g_q)[(size_t)R * DH + d]);
  float mx = -INFINITY;
  for (int pass = 0; pass < 2; pass++) {
    float l = 0.f, o[DH];
#pragma unroll
    for (int d = 0; d < DH; d++) o[d] = 0.f;
    for (int k = lane; k < S_LEN; k += 32) {
      const __half* kp = (const __half*)(smem + (k >> 3) * 384 + (k & 7) * 16);
      float s = 0.f;
#pragma unroll
      for (int d = 0; d < DH; d++) s = fmaf(q[d], __half2float(kp[(d >> 3) * 64 + (d & 7)]), s);
      if (pass == 0) mx = fmaxf(mx, s);
      else {
        float pr = exp2f(s - mx);
        l += pr;
        const bf16* vp = (const bf16*)((const uint8_t*)kp + S_LEN * 48);
#pragma unroll
        for (int d = 0; d < DH; d++) o[d] = fmaf(pr, __bfloat162float(vp[(d >> 3) * 64 + (d & 7)]), o[d]);
      }
    }
    if (pass == 0) {
      for (int s = 16; s; s >>= 1) mx = fmaxf(mx, __shfl_xor_sync(~0u, mx, s));
    } else {
      for (int s = 16; s; s >>= 1) {
        l += __shfl_xor_sync(~0u, l, s);
#pragma unroll
        for (int d = 0; d < DH; d++) o[d] += __shfl_xor_sync(~0u, o[d], s);
      }
      if (lane == 0) {
        bf16* dst = g_oh + (size_t)(R >> 5) * (DM + FF) + (R & 31) * DH;
#pragma unroll
        for (int d = 0; d < DH; d++) dst[d] = __float2bfloat16(o[d] / l);
      }
    }
  }
}

#define TLA(j)
#define ATT_NP 5
constexpr int ATT_SMEM = S_LEN * 96 + 256;
__global__ void __launch_bounds__(512, 1) attn_kernel(const bf16* __restrict__ wo, const bf16* __restrict__ wd) {
  extern __shared__ __align__(1024) uint8_t smem[];
  const uint32_t sb = smem_u32(smem), bars = sb + S_LEN * 96;
  const int tid = threadIdx.x, wg = tid >> 7, lane = tid & 31, g = lane >> 2, c = lane & 3, w = (tid >> 5) & 3;
  if (tid == 0) {
    for (int i = 0; i < 16; i++) mbar_init(bars + 8 * i, 1);
    fence_mbar_init();
  }
  __syncthreads();
  TLA(0);
  if (tid == 64) {
    l2_prefetch((const char*)wo + blockIdx.x * 6400, 6400);
    l2_prefetch((const char*)wd + blockIdx.x * 15360, 15360);
  }
  pdl_wait();
  pdl_trigger();
  TLA(1);
  const int rot = 0;
  if (tid == 0) {
    mbar_expect(bars + 8 * rot, 12288);
    bulk_g2s(sb + rot * 6144, g_kimg + rot * 6144, 6144, bars + 8 * rot);
    bulk_g2s(sb + S_LEN * 48 + rot * 6144, g_vimg + rot * 6144, 6144, bars + 8 * rot);
  }
  uint32_t qn[6];
  {
    const uint32_t* qp0 = (const uint32_t*)(g_q + (size_t)(blockIdx.x * 512 + wg * 128 + w * 16 + g) * DH);
    const uint32_t* qp1 = qp0 + 8 * (DH / 2);
    qn[0] = qp0[c]; qn[1] = qp1[c]; qn[2] = qp0[c + 4]; qn[3] = qp1[c + 4];
    qn[4] = c < 2 ? qp0[8 + c] : 0u; qn[5] = c < 2 ? qp1[8 + c] : 0u;
  }
  const uint64_t dK0 = mkdesc(sb, 128, 384, 0), dK1 = mkdesc(sb + 256, 0, 384, 0), dV = mkdesc(sb + S_LEN * 48, 384, 128, 0);
#pragma unroll 1
  for (int mt = 0; mt < 2; mt++) {
    const int R0 = blockIdx.x * 512 + wg * 128 + mt * 64 + w * 16 + g;
    uint32_t qa0 = qn[0], qa1 = qn[1], qa2 = qn[2], qa3 = qn[3], qb0 = qn[4], qb1 = qn[5];
    if (mt == 0) {
      const uint32_t* qp0 = (const uint32_t*)(g_q + (size_t)(R0 + 64) * DH);
      const uint32_t* qp1 = qp0 + 8 * (DH / 2);
      qn[0] = qp0[c]; qn[1] = qp1[c]; qn[2] = qp0[c + 4]; qn[3] = qp1[c + 4];
      qn[4] = c < 2 ? qp0[8 + c] : 0u; qn[5] = c < 2 ? qp1[8 + c] : 0u;
    }
    float o[12];
    mbar_wait(bars + 8 * rot, 0);
    if (mt == 0 && lane == 0 && tid >= 32) {
      const uint32_t i = ((tid >> 5) + rot) & 15;
      mbar_expect(bars + 8 * i, 12288);
      bulk_g2s(sb + i * 6144, g_kimg + i * 6144, 6144, bars + 8 * i);
      bulk_g2s(sb + S_LEN * 48 + i * 6144, g_vimg + i * 6144, 6144, bars + 8 * i);
    }
    __syncwarp();
    TLA(2 + mt * 4);
    {
      uint32_t s[16], s2[16];
      wg_fence();
      wgmma_h_m64n64k16_rs(s, qa0, qa1, qa2, qa3, dK0 + rot * 384, 0);
      wgmma_h_m64n64k16_rs(s2, qa0, qa1, qa2, qa3, dK0 + rot * 384 + 192, 0);
      wgmma_h_m64n64k16_rs(s, qb0, qb1, 0u, 0u, dK1 + rot * 384, 1);
      wgmma_h_m64n64k16_rs(s2, qb0, qb1, 0u, 0u, dK1 + rot * 384 + 192, 1);
      wg_commit();
      wg_wait<0>();
      ureg_fence(s); ureg_fence(s2);
      uint32_t mx0 = hmax2(s[0], s2[0]), mx1 = hmax2(s[1], s2[1]), mn0 = hmin2(s[0], s2[0]), mn1 = hmin2(s[1], s2[1]);
#pragma unroll
      for (int i = 2; i < 16; i += 2) {
        mx0 = hmax2(mx0, hmax2(s[i], s2[i])); mx1 = hmax2(mx1, hmax2(s[i + 1], s2[i + 1]));
        mn0 = hmin2(mn0, hmin2(s[i], s2[i])); mn1 = hmin2(mn1, hmin2(s[i + 1], s2[i + 1]));
      }
#pragma unroll
      for (int d = 1; d < 4; d <<= 1) {
        mx0 = hmax2(mx0, __shfl_xor_sync(~0u, mx0, d)); mx1 = hmax2(mx1, __shfl_xor_sync(~0u, mx1, d));
        mn0 = hmin2(mn0, __shfl_xor_sync(~0u, mn0, d)); mn1 = hmin2(mn1, __shfl_xor_sync(~0u, mn1, d));
      }
      const float M0 = fmaxf(hlo(mx0), hhi(mx0)), M1 = fmaxf(hlo(mx1), hhi(mx1));
      const float h0 = fminf(64.f, 0.5f * (M0 - fminf(hlo(mn0), hhi(mn0)))), h1 = fminf(64.f, 0.5f * (M1 - fminf(hlo(mn1), hhi(mn1))));
      if (c == 2) {
        qb0 = 0x3C000000u | __half_as_ushort(__float2half_rn(-(M0 + h0)));
        qb1 = 0x3C000000u | __half_as_ushort(__float2half_rn(-(M1 + h1)));
      }
    }
#pragma unroll
    for (int i = 0; i < 12; i++) o[i] = 0.f;
    TLA(3 + mt * 4);
#pragma unroll 1
    for (int jj = 0; jj < 16; jj++) {
      const int j = (jj + rot) & 15;
      mbar_wait(bars + 8 * j, 0);
#pragma unroll
      for (int h = 0; h < 2; h++) {
        float sf[ATT_NM * 4];
        uint32_t sh[(8 - ATT_NM) * 2];
        const uint64_t k0 = dK0 + j * 384 + h * 192, k1 = dK1 + j * 384 + h * 192;
        wg_fence();
        wgmma_hf_rs(sf, qa0, qa1, qa2, qa3, k0, 0);
        wgmma_hh_rs(sh, qa0, qa1, qa2, qa3, k0 + ATT_NM * 24, 0);
        wgmma_hf_rs(sf, qb0, qb1, 0u, 0u, k1, 1);
        wgmma_hh_rs(sh, qb0, qb1, 0u, 0u, k1 + ATT_NM * 24, 1);
        wg_commit();
        wg_wait<0>();
        reg_fence(sf); ureg_fence(sh);
        uint32_t p[16];
#pragma unroll
        for (int i = 0; i < 16; i++) {
          const int a = i >> 1;
          if ((i & 1) == 0) { if (a < 2 * ATT_NM) p[a] = packbf(ex2(sf[2 * a]), ex2(sf[2 * a + 1])); }
          else if (a < 16 - 2 * ATT_NM) p[2 * ATT_NM + a] = exp2_pair_h(sh[a]);
        }
#pragma unroll
        for (int a = 8; a < 2 * ATT_NM; a++) p[a] = packbf(ex2(sf[2 * a]), ex2(sf[2 * a + 1]));
#pragma unroll
        for (int a = 8; a < 16 - 2 * ATT_NM; a++) p[2 * ATT_NM + a] = exp2_pair_h(sh[a]);
        wg_fence();
#pragma unroll
        for (int k = 0; k < 4; k++)
          wgmma_m64n24k16_rs_tb1(o, p[4 * k], p[4 * k + 1], p[4 * k + 2], p[4 * k + 3], dV + j * 384 + h * 192 + k * 48, 1);
        wg_commit();
      }
    }
    wg_wait<0>();
    reg_fence(o);
    TLA(4 + mt * 4);
    const float l0 = __shfl_sync(~0u, o[8], (lane & ~3) | 2), l1 = __shfl_sync(~0u, o[10], (lane & ~3) | 2);
    bool bad0 = !(l0 < 4e34f) || !(l0 > 0.f), bad1 = !(l1 < 4e34f) || !(l1 > 0.f);
#pragma unroll
    for (int i = 0; i < 12; i += 4) {
      bad0 |= !(fabsf(o[i]) < INFINITY) || !(fabsf(o[i + 1]) < INFINITY);
      bad1 |= !(fabsf(o[i + 2]) < INFINITY) || !(fabsf(o[i + 3]) < INFINITY);
    }
    const float r0 = 1.f / l0, r1 = 1.f / l1;
    uint32_t* op0 = (uint32_t*)(g_oh + (size_t)(R0 >> 5) * (DM + FF) + (R0 & 31) * DH);
    uint32_t* op1 = op0 + 8 * (DH / 2);
    op0[c] = packbf(o[0] * r0, o[1] * r0); op0[c + 4] = packbf(o[4] * r0, o[5] * r0);
    op1[c] = packbf(o[2] * r1, o[3] * r1); op1[c + 4] = packbf(o[6] * r1, o[7] * r1);
    if (c < 2) { op0[c + 8] = packbf(o[8] * r0, o[9] * r0); op1[c + 8] = packbf(o[10] * r1, o[11] * r1); }
    TLA(5 + mt * 4);
    const uint32_t bm0 = __ballot_sync(~0u, bad0), bm1 = __ballot_sync(~0u, bad1);
    if (bm0 | bm1) {
      __syncwarp();
      for (int r = 0; r < 8; r++) {
        if ((bm0 >> (4 * r)) & 15) attn_row_exact(smem, R0 - g + r);
        if ((bm1 >> (4 * r)) & 15) attn_row_exact(smem, R0 - g + r + 8);
      }
    }
  }
}
}

namespace {
#define TLREC(k, j)
__global__ void __launch_bounds__(256) ln_kernel(const bf16* __restrict__ x, const bf16* __restrict__ wq, const bf16* __restrict__ wk,
                                                 const bf16* __restrict__ wv, const bf16* __restrict__ wg, const bf16* __restrict__ wu) {
  pdl_trigger();
  const int warp = threadIdx.x >> 5, lane = threadIdx.x & 31;
  if (blockIdx.x >= 256) {
    const int i0 = ((blockIdx.x - 256) * 256 + threadIdx.x) * 4, r = i0 >> 7, c0 = i0 & 127;
    bf16 v[4];
#pragma unroll
    for (int j = 0; j < 4; j++) {
      const int cI = c0 + j;
      v[j] = cI < 24 ? wq[r * DM + 616 + cI] : cI < 44 ? wk[r * DH + cI - 24] : (cI >= 48 && cI < 68) ? wv[r * DH + cI - 48] : __float2bfloat16(0.f);
    }
    *(uint2*)(g_wpk + i0) = *(const uint2*)v;
    return;
  }
  const int row = blockIdx.x * 8 + warp;
  const uint4* src = (const uint4*)(x + (size_t)row * DM);
  uint4 v[3];
  v[0] = src[lane]; v[1] = src[lane + 32]; v[2] = lane < 16 ? src[lane + 64] : make_uint4(0, 0, 0, 0);
  float f[24];
#pragma unroll
  for (int i = 0; i < 3; i++) {
    const uint32_t u[4] = {v[i].x, v[i].y, v[i].z, v[i].w};
#pragma unroll
    for (int j = 0; j < 4; j++) { f[i * 8 + 2 * j] = bflo(u[j]); f[i * 8 + 2 * j + 1] = bfhi(u[j]); }
  }
  float s = 0.f;
#pragma unroll
  for (int i = 0; i < 24; i++) s += f[i];
  for (int o = 16; o; o >>= 1) s += __shfl_xor_sync(~0u, s, o);
  const float mean = s * (1.f / DM);
  if (threadIdx.x == 0) {
    l2_prefetch((const char*)wg + blockIdx.x * 7680, 7680);
    l2_prefetch((const char*)wu + blockIdx.x * 7680, 7680);
    l2_prefetch((const char*)wq + blockIdx.x * 3200, 3200);
  }
  float q = 0.f;
#pragma unroll
  for (int i = 0; i < 24; i++) { const float d = (i < 16 || lane < 16) ? f[i] - mean : 0.f; f[i] = d; q = fmaf(d, d, q); }
  for (int o = 16; o; o >>= 1) q += __shfl_xor_sync(~0u, q, o);
  const float rs = rsqrtf(q * (1.f / DM) + 1e-5f);
  uint4* dst = (uint4*)(g_xn + (size_t)row * DM);
#pragma unroll
  for (int i = 0; i < 3; i++) {
    uint4 o;
    o.x = packbf(f[i * 8] * rs, f[i * 8 + 1] * rs); o.y = packbf(f[i * 8 + 2] * rs, f[i * 8 + 3] * rs);
    o.z = packbf(f[i * 8 + 4] * rs, f[i * 8 + 5] * rs); o.w = packbf(f[i * 8 + 6] * rs, f[i * 8 + 7] * rs);
    if (i < 2 || lane < 16) dst[lane + 32 * i] = o;
  }
}

constexpr int P_A = 0, P_B = 163840, P_BAR = P_B + 4 * 16384, PRE_SMEM = P_BAR + 1024;
__device__ __forceinline__ float gelu_tanh(float a) {
  const float u = a * fmaf(a * a, 0.7978845608f * 0.044715f, 0.7978845608f);
  float t; asm("tanh.approx.f32 %0, %1;" : "=f"(t) : "f"(u));
  const float h = 0.5f * a;
  return fmaf(h, t, h);
}
__device__ __forceinline__ void st_pair8(uint32_t* base, int c, uint32_t v0, uint32_t v1) {
  const uint32_t send = (c & 1) ? v0 : v1, got = __shfl_xor_sync(~0u, send, 1);
  uint2 o = (c & 1) ? make_uint2(got, v1) : make_uint2(v0, got);
  *(uint2*)(base + ((c & 1) ? 4 + (c - 1) : c)) = o;
}
template <int N>
__device__ __forceinline__ void pre_mma(float (&a0)[N / 2], float (&a1)[N / 2], uint32_t sb, int job2, int wg) {
  const uint32_t bars = sb + P_BAR;
  const int tid = threadIdx.x & 127;
  int prev = -1;
#pragma unroll 1
  for (int k = 0; k < 10; k++) {
    const int i = job2 ? 20 + (wg == 0 ? (k < 4 ? k : 2 * k - 3) : (k < 6 ? 4 + 2 * k : 10 + k)) : (wg == 0 ? (k < 3 ? k : 2 * k - 2) : (k < 7 ? 3 + 2 * k : 10 + k));
    const int slot = i & 3;
    const bool ready = __all_sync(~0u, mbar_test(bars + 8 * (10 + i), 0) && (job2 || mbar_test(bars + 8 * k, 0)));
    if (!ready) {
      if (prev >= 0) {
        wg_wait<0>();
        if (tid == 0) mbar_arrive_remote(bars + 8 * (50 + prev), 0);
        if (tid == 32) mbar_arrive_remote(bars + 8 * (50 + prev), 1);
        prev = -1;
      }
      if (!job2) mbar_wait(bars + 8 * k, 0);
      mbar_wait(bars + 8 * (10 + i), 0);
    }
    if (tid == 0) TLREC(0, 40 + i);
    const uint64_t dA = mkdesc(sb + P_A + k * 16384, 16, 1024, 1), dB = mkdesc(sb + P_B + slot * 16384, 8192, 1024, 1);
    wg_fence();
#pragma unroll
    for (int s = 0; s < 4; s++) {
      if (N == 128) {
        wgmma_m64n128k16_ss_tb1((float(&)[64])a0, dA + s * 2, dB + s * 128, (k | s) != 0);
        wgmma_m64n128k16_ss_tb1((float(&)[64])a1, dA + 512 + s * 2, dB + s * 128, (k | s) != 0);
      } else {
        wgmma_m64n88k16_ss_tb1((float(&)[44])a0, dA + s * 2, dB + s * 128, (k | s) != 0);
        wgmma_m64n88k16_ss_tb1((float(&)[44])a1, dA + 512 + s * 2, dB + s * 128, (k | s) != 0);
      }
    }
    wg_commit();
    if (prev >= 0) {
      wg_wait<1>();
      if (tid == 0) mbar_arrive_remote(bars + 8 * (50 + prev), 0);
      if (tid == 32) mbar_arrive_remote(bars + 8 * (50 + prev), 1);
    }
    prev = i;
  }
  wg_wait<0>();
  if (tid == 0) mbar_arrive_remote(bars + 8 * (50 + prev), 0);
  if (tid == 32) mbar_arrive_remote(bars + 8 * (50 + prev), 1);
  reg_fence(a0); reg_fence(a1);
}
__device__ __forceinline__ void glu_epi(const float (&a)[64], int row, int col0, int c) {
  uint32_t* p0 = (uint32_t*)(g_oh + (size_t)row * (DM + FF) + DM + col0);
  uint32_t* p1 = p0 + 8 * ((DM + FF) / 2);
#pragma unroll
  for (int j = 0; j < 8; j += 2) {
    uint32_t v[4];
#pragma unroll
    for (int t = 0; t < 2; t++) {
      const int b = (j + t) * 4;
      v[t] = packbf(gelu_tanh(a[b]) * a[32 + b], gelu_tanh(a[b + 1]) * a[33 + b]);
      v[2 + t] = packbf(gelu_tanh(a[b + 2]) * a[34 + b], gelu_tanh(a[b + 3]) * a[35 + b]);
    }
    st_pair8(p0 + j * 4, c, v[0], v[1]);
    st_pair8(p1 + j * 4, c, v[2], v[3]);
  }
}
constexpr float QSCALE = 0.22360679774997896f * 1.4426950408889634f;
__device__ __forceinline__ void qkv_epi(const float (&a0)[44], const float (&a1)[44], uint8_t* stg, int mt, int ng) {
  const int t = threadIdx.x & 127, lane = t & 31, g = lane >> 2, c = lane & 3, w = t >> 5;
  const int nq = ng < 7 ? 11 : 3;
#pragma unroll
  for (int h = 0; h < 2; h++) {
    const float(&a)[44] = h ? a1 : a0;
    uint32_t* p0 = (uint32_t*)(stg + (h * 64 + w * 16 + g) * 176) + c;
#pragma unroll
    for (int j = 0; j < 11; j++) {
      const float sc = j < nq ? QSCALE : 1.f;
      uint32_t v0, v1;
      if (ng == 7 && j >= 6) { v0 = packbf(a[4 * j], a[4 * j + 1]); v1 = packbf(a[4 * j + 2], a[4 * j + 3]); }
      else { v0 = packh(a[4 * j] * sc, a[4 * j + 1] * sc); v1 = packh(a[4 * j + 2] * sc, a[4 * j + 3] * sc); }
      if (ng == 7 && c >= 2) {
        if (j == 8) v0 = v1 = (c == 2) ? 0x00003F80u : 0u;
        if (j == 5) {
          v0 = (c == 2) ? (0x3C00u | (((ATT_PMASK >> (2 * w)) & 1) ? 0xB8000000u : 0u)) : 0u;
          v1 = (c == 2) ? (0x3C00u | (((ATT_PMASK >> (2 * w + 1)) & 1) ? 0xB8000000u : 0u)) : 0u;
        }
      }
      p0[j * 4] = v0;
      p0[j * 4 + 8 * 44] = v1;
    }
  }
  asm volatile("bar.sync 1, 128;" ::: "memory");
#pragma unroll
  for (int i = 0; i < 11; i++) {
    const int idx = i * 128 + t, r = idx / 11, j = idx - r * 11, row = mt * 128 + r;
    const uint4 v = *(const uint4*)(stg + r * 176 + j * 16);
    if (j < nq) *(uint4*)(g_q + (size_t)row * DM + (ng < 7 ? ng * 88 : 616) + j * 8) = v;
    else if (j < 9) *(uint4*)((j < 6 ? g_kimg : g_vimg) + (row >> 3) * 384 + (j % 3) * 128 + (row & 7) * 16) = v;
  }
}
__global__ void __cluster_dims__(2, 1, 1) __launch_bounds__(384, 1)
pre_kernel(const __grid_constant__ CUtensorMap tmA, const __grid_constant__ CUtensorMap tmG, const __grid_constant__ CUtensorMap tmU,
           const __grid_constant__ CUtensorMap tmQ, const __grid_constant__ CUtensorMap tmP) {
  extern __shared__ __align__(1024) uint8_t smem[];
  const uint32_t sb = smem_u32(smem), bars = sb + P_BAR;
  const int tid = threadIdx.x, wg = tid >> 7, rank = cta_rank();
  const int mt = blockIdx.x & 15, ng = blockIdx.x >> 4;
  if (tid == 0) {
    for (int i = 0; i < 50; i++) mbar_init(bars + 8 * i, 1);
    for (int i = 50; i < 90; i++) mbar_init(bars + 8 * i, 2);
    fence_mbar_init();
  }
  __syncthreads();
  asm volatile("barrier.cluster.arrive.relaxed.aligned;\nbarrier.cluster.wait.aligned;" ::: "memory");
  pdl_trigger();
  if (tid == 0) TLREC(0, 100);
  if (wg == 2) {
    const int w = (tid >> 5) & 3;
    if (w == 0 && (tid & 31) == 0) {
      const CUtensorMap* tq = ng < 7 ? &tmQ : &tmP;
#pragma unroll 1
      for (int i = 0; i < 40; i++) {
        int job, k;
        if (i >= 20) {
          const int j = i - 24;
          if (j < 0) { job = 2; k = i - 20; }
          else if (j >= 12) { job = 3; k = i - 30; }
          else if (j & 1) { job = 2; k = 4 + (j >> 1); }
          else { job = 3; k = j >> 1; }
        }
        else if (i < 3) { job = 0; k = i; }
        else if (i >= 17) { job = 1; k = i - 10; }
        else if ((i - 3) & 1) { job = 0; k = 3 + ((i - 3) >> 1); }
        else { job = 1; k = (i - 3) >> 1; }
        const int slot = i & 3;
        if (i >= 4) mbar_wait(bars + 8 * (46 + i), 0);
        if (i == 24) pdl_wait();
        TLREC(0, i);
        mbar_expect(bars + 8 * (10 + i), 16384);
        const uint32_t dst = sb + P_B + slot * 16384 + rank * 8192;
        if (job < 3) tma_2d_mc(dst, rank ? &tmU : &tmG, (ng * 3 + job) * 64, k * 64, bars + 8 * (10 + i), 3);
        else tma_2d_mc(dst, tq, (ng < 7 ? ng * 88 : 0) + rank * 64, k * 64, bars + 8 * (10 + i), 3);
      }
    } else if (w == 1 && (tid & 31) == 0) {
      pdl_wait();
#pragma unroll 1
      for (int k = 0; k < 10; k++) {
        mbar_expect(bars + 8 * k, 16384);
        tma_2d(sb + P_A + k * 16384, &tmA, k * 64, mt * 128, bars + 8 * k);
      }
    }
  } else {
    const int lane = tid & 31, g = lane >> 2, c = lane & 3, w = (tid >> 5) & 3;
    const int row = mt * 128 + w * 16 + g;
    {
      float a0[64], a1[64];
      pre_mma<128>(a0, a1, sb, 0, wg);
      glu_epi(a0, row, (ng * 3 + wg) * 64, c);
      glu_epi(a1, row + 64, (ng * 3 + wg) * 64, c);
    }
    if (wg == 0) {
      float a0[64], a1[64];
      pre_mma<128>(a0, a1, sb, 1, 0);
      glu_epi(a0, row, (ng * 3 + 2) * 64, c);
      glu_epi(a1, row + 64, (ng * 3 + 2) * 64, c);
    } else {
      float a0[44], a1[44];
      pre_mma<88>(a0, a1, sb, 1, 1);
      qkv_epi(a0, a1, smem + P_B, mt, ng);
    }
  }
  if (tid == 0) TLREC(0, 101);
  if (tid == 128) TLREC(0, 102);
  __syncwarp();
  asm volatile("barrier.cluster.arrive.relaxed.aligned;\nbarrier.cluster.wait.aligned;" ::: "memory");
}

constexpr int O_ST = 36864, O_NS = 5, O_X = O_NS * O_ST, O_BAR = O_X + 40960, POST_SMEM = O_BAR + 256;
__global__ void __cluster_dims__(2, 1, 1) __launch_bounds__(384, 1)
post_kernel(const __grid_constant__ CUtensorMap tmA, const __grid_constant__ CUtensorMap tmO, const __grid_constant__ CUtensorMap tmD,
            const bf16* __restrict__ x, bf16* __restrict__ out) {
  extern __shared__ __align__(1024) uint8_t smem[];
  const uint32_t sb = smem_u32(smem), bars = sb + O_BAR;
  const int tid = threadIdx.x, wg = tid >> 7, rank = cta_rank();
  const int tile = blockIdx.x >> 1, mt = tile >> 2, nt = tile & 3;
  if (tid == 0) {
    for (int i = 0; i < O_NS; i++) { mbar_init(bars + 8 * i, 2); mbar_init(bars + 8 * (5 + i), 2); }
    mbar_init(bars + 80, 1);
    mbar_expect(bars + 80, 40960);
    fence_mbar_init();
  }
  __syncthreads();
  asm volatile("barrier.cluster.arrive.relaxed.aligned;\nbarrier.cluster.wait.aligned;" ::: "memory");
  if (tid == 0) TLREC(1, 100);
  if (wg == 2) {
    const int w = (tid >> 5) & 3;
    if (w < 2 && (tid & 31) == 0) {
#pragma unroll 1
      for (int i = 0; i < 17; i++) {
        const int slot = i % O_NS, hc = rank ? 17 + i : i;
        if (i >= O_NS) mbar_wait(bars + 8 * (5 + slot), (i / O_NS - 1) & 1);
        if (w == 0) {
          TLREC(1, i);
          if (hc == 24) pdl_wait();
          mbar_expect(bars + 8 * slot, 16384);
          tma_2d(sb + slot * O_ST, &tmA, hc < 24 ? DM + hc * 64 : (hc - 24) * 64, mt * 128, bars + 8 * slot);
        } else {
          mbar_expect(bars + 8 * slot, 20480);
          tma_3d(sb + slot * O_ST + 16384, hc < 24 ? &tmD : &tmO, 0, (hc < 24 ? hc : hc - 24) * 64, nt * 5, bars + 8 * slot);
        }
      }
    }
  } else {
    const int lane = tid & 31, g = lane >> 2, c = lane & 3, w = (tid >> 5) & 3, t = tid & 127;
    float a[80];
    const int row = mt * 128 + wg * 64 + w * 16 + g;
    uint32_t xv[20];
    {
      const uint32_t* x0 = (const uint32_t*)(x + (size_t)row * DM + nt * 160 + rank * 80) + c;
#pragma unroll
      for (int j = 0; j < 10; j++) { xv[2 * j] = __ldg(x0 + j * 4); xv[2 * j + 1] = __ldg(x0 + 8 * (DM / 2) + j * 4); }
    }
    int prev = -1;
#pragma unroll 1
    for (int i = 0; i < 17; i++) {
      const int slot = i % O_NS;
      if (!__all_sync(~0u, mbar_test(bars + 8 * slot, (i / O_NS) & 1))) {
        if (prev >= 0) { wg_wait<0>(); if (t == 0) mbar_arrive(bars + 8 * (5 + prev)); prev = -1; }
        mbar_wait(bars + 8 * slot, (i / O_NS) & 1);
      }
      if (tid == 0) TLREC(1, 40 + i);
      const uint64_t dA = mkdesc(sb + slot * O_ST + wg * 8192, 16, 1024, 1), dB = mkdesc(sb + slot * O_ST + 16384, 4096, 512, 2);
      wg_fence();
#pragma unroll
      for (int s = 0; s < 4; s++) wgmma_m64n160k16_ss_tb1(a, dA + s * 2, dB + s * 64, (i | s) != 0);
      wg_commit();
      if (prev >= 0) { wg_wait<1>(); if (t == 0) mbar_arrive(bars + 8 * (5 + prev)); }
      prev = slot;
    }
    wg_wait<0>();
    reg_fence(a);
    if (tid == 0) TLREC(1, 101);
    {
      const uint32_t dst = mapa(sb + O_X + wg * 20480 + t * 16, rank ^ 1), rbar = mapa(bars + 80, rank ^ 1);
      float keep[40];
#pragma unroll
      for (int j = 0; j < 10; j++) {
        const int b = 4 * j;
        const float s0 = rank ? a[b] : a[40 + b], s1 = rank ? a[b + 1] : a[41 + b], s2 = rank ? a[b + 2] : a[42 + b], s3 = rank ? a[b + 3] : a[43 + b];
        asm volatile("st.async.weak.shared::cluster.mbarrier::complete_tx::bytes.v4.f32 [%0], {%1,%2,%3,%4}, [%5];" ::"r"(dst + j * 2048), "f"(s0), "f"(s1), "f"(s2), "f"(s3), "r"(rbar) : "memory");
      }
#pragma unroll
      for (int i = 0; i < 40; i++) keep[i] = rank ? a[40 + i] : a[i];
      mbar_wait(bars + 80, 0);
      uint32_t* o0 = (uint32_t*)(out + (size_t)row * DM + nt * 160 + rank * 80);
#pragma unroll
      for (int j = 0; j < 10; j += 2) {
        uint32_t v[4];
#pragma unroll
        for (int u = 0; u < 2; u++) {
          const float4 p = *(const float4*)(smem + O_X + wg * 20480 + (j + u) * 2048 + t * 16);
          const int b = 4 * (j + u);
          v[u] = packbf(keep[b] + p.x + bflo(xv[2 * (j + u)]), keep[b + 1] + p.y + bfhi(xv[2 * (j + u)]));
          v[2 + u] = packbf(keep[b + 2] + p.z + bflo(xv[2 * (j + u) + 1]), keep[b + 3] + p.w + bfhi(xv[2 * (j + u) + 1]));
        }
        st_pair8(o0 + j * 4, c, v[0], v[1]);
        st_pair8(o0 + 8 * (DM / 2) + j * 4, c, v[2], v[3]);
      }
      if (t == 0) TLREC(1, 102);
    }
  }
}
}

namespace {
typedef CUresult (*EncFn)(CUtensorMap*, CUtensorMapDataType, cuuint32_t, void*, const cuuint64_t*, const cuuint64_t*, const cuuint32_t*, const cuuint32_t*,
                          CUtensorMapInterleave, CUtensorMapSwizzle, CUtensorMapL2promotion, CUtensorMapFloatOOBfill);
void enc2d(EncFn f, CUtensorMap* m, const void* p, uint64_t cols, uint64_t rows, uint32_t bc, uint32_t br) {
  cuuint64_t d[2] = {cols, rows}, s[1] = {cols * 2};
  cuuint32_t b[2] = {bc, br}, e[2] = {1, 1};
  f(m, CU_TENSOR_MAP_DATA_TYPE_BFLOAT16, 2, (void*)p, d, s, b, e, CU_TENSOR_MAP_INTERLEAVE_NONE, CU_TENSOR_MAP_SWIZZLE_128B, CU_TENSOR_MAP_L2_PROMOTION_L2_256B, CU_TENSOR_MAP_FLOAT_OOB_FILL_NONE);
}
void enc3d(EncFn f, CUtensorMap* m, const void* p, uint64_t rows) {
  cuuint64_t d[3] = {32, rows, 20}, s[2] = {DM * 2, 64};
  cuuint32_t b[3] = {32, 64, 5}, e[3] = {1, 1, 1};
  f(m, CU_TENSOR_MAP_DATA_TYPE_BFLOAT16, 3, (void*)p, d, s, b, e, CU_TENSOR_MAP_INTERLEAVE_NONE, CU_TENSOR_MAP_SWIZZLE_64B, CU_TENSOR_MAP_L2_PROMOTION_L2_256B, CU_TENSOR_MAP_FLOAT_OOB_FILL_NONE);
}
template <typename... KA, typename... A>
void launch_pdl(void (*k)(KA...), int grid, int block, int smem, bool pdl, A... a) {
  cudaLaunchConfig_t c = {};
  c.gridDim = grid; c.blockDim = block; c.dynamicSmemBytes = smem; c.stream = cudaStreamPerThread;
  cudaLaunchAttribute at[1];
  at[0].id = cudaLaunchAttributeProgrammaticStreamSerialization; at[0].val.programmaticStreamSerializationAllowed = 1;
  c.attrs = at; c.numAttrs = pdl ? 1 : 0;
  cudaLaunchKernelEx(&c, k, a...);
}
}
extern "C" void kernel_launch(void* const* d_in, const int* in_sizes, int n_in, void* d_out, int out_size) {
  const bf16* x = (const bf16*)d_in[0];
  static bool init = false;
  static EncFn f = nullptr;
  static void *pxn, *pwpk, *poh;
  if (!init) {
    void* fp = nullptr; cudaDriverEntryPointQueryResult qr;
    cudaGetDriverEntryPoint("cuTensorMapEncodeTiled", &fp, cudaEnableDefault, &qr);
    f = (EncFn)fp;
    cudaGetSymbolAddress(&pxn, g_xn); cudaGetSymbolAddress(&pwpk, g_wpk); cudaGetSymbolAddress(&poh, g_oh);
    cudaFuncSetAttribute(attn_kernel, cudaFuncAttributeMaxDynamicSharedMemorySize, ATT_SMEM);
    cudaFuncSetAttribute(pre_kernel, cudaFuncAttributeMaxDynamicSharedMemorySize, PRE_SMEM);
    cudaFuncSetAttribute(post_kernel, cudaFuncAttributeMaxDynamicSharedMemorySize, POST_SMEM);
    init = true;
  }
  CUtensorMap tXn, tG, tU, tQ, tP, tOH, tO, tD;
  enc2d(f, &tXn, pxn, DM, S_LEN, 64, 128); enc2d(f, &tG, d_in[6], FF, DM, 64, 64); enc2d(f, &tU, d_in[7], FF, DM, 64, 64);
  enc2d(f, &tQ, d_in[1], DM, DM, 64, 64); enc2d(f, &tP, pwpk, 128, DM, 64, 64); enc2d(f, &tOH, poh, DM + FF, S_LEN, 64, 128);
  enc3d(f, &tO, d_in[4], DM); enc3d(f, &tD, d_in[8], FF);
  launch_pdl(ln_kernel, 336, 256, 0, false, x, (const bf16*)d_in[1], (const bf16*)d_in[2], (const bf16*)d_in[3], (const bf16*)d_in[6], (const bf16*)d_in[7]);
  launch_pdl(pre_kernel, 128, 384, PRE_SMEM, true, tXn, tG, tU, tQ, tP);
  launch_pdl(attn_kernel, 128, 512, ATT_SMEM, true, (const bf16*)d_in[4], (const bf16*)d_in[8]);
  launch_pdl(post_kernel, 128, 384, POST_SMEM, true, tOH, tO, tD, x, (bf16*)d_out);
}
```
